```python
import torch

def _softmax(x, axis=-1):
    return torch.softmax(x, dim=axis)
def _gelu(x):
    return torch.nn.functional.gelu(x, approximate="tanh")
def _silu(x):
    return torch.nn.functional.silu(x)
def _sigmoid(x):
    return torch.sigmoid(x)
def _layernorm(x, axis=-1, eps=1e-5):
    m = x.mean(dim=axis, keepdim=True)
    v = x.var(dim=axis, keepdim=True, unbiased=False)
    return (x - m) / torch.sqrt(v + eps)
def _scatter_add(tgt, idx, src, axis=0):
    return tgt.clone().index_add_(axis, idx, src)
def _segment_sum(src, seg, n):
    out = torch.zeros((n,) + src.shape[1:], dtype=src.dtype)
    return out.index_add_(0, seg, src)
def _pad(x, pw):
    flat = tuple(v for pair in reversed(pw) for v in pair)
    return torch.nn.functional.pad(x, flat)

kernel_name = 'interleave_layers__linear_kernel_hedgehog__mixer_token_mlp__prompt'

def setup_inputs():

    _w = (lambda a: (lambda t: t.to(torch.bfloat16) if t.is_floating_point() else t)(torch.as_tensor(a)))
    def _A_setup():
        B, S, D, H = 1, 2048, 640, 32
        Dh = D // H
        return {
            "x": _w((lambda *s: torch.randn(*s, dtype=torch.bfloat16) * 0.05)(B, S, D)),
            "wqkv": _w((lambda *s: torch.randn(*s, dtype=torch.bfloat16) * 0.4)(D, 3 * D)),
            "w_phi": _w((lambda *s: torch.randn(*s, dtype=torch.bfloat16) * 0.4)(H, Dh, Dh) * (Dh ** -0.5)),
            "wo": _w((lambda *s: torch.randn(*s, dtype=torch.bfloat16) * 0.05)(D, D)),
        }
    _A_in = _A_setup()

    def _B_setup():
        B, S, D, F = 1, 2048, 640, 1536
        return {
            "x": _w((lambda *s: torch.randn(*s, dtype=torch.bfloat16) * 0.05)(B, S, D)),
            "w1": _w((lambda *s: torch.randn(*s, dtype=torch.bfloat16) * 0.8)(S, F) * (S ** -0.5)),
            "b1": _w((lambda *s: torch.randn(*s, dtype=torch.bfloat16) * 0.8)(F) * 0.02),
            "w2": _w((lambda *s: torch.randn(*s, dtype=torch.bfloat16) * 0.8)(F, S) * (F ** -0.5)),
            "b2": _w((lambda *s: torch.randn(*s, dtype=torch.bfloat16) * 0.8)(S) * 0.02),
        }
    _B_in = _B_setup()

    return {
        "A_x": _A_in["x"],
        "A_wqkv": _A_in["wqkv"],
        "A_w_phi": _A_in["w_phi"],
        "A_wo": _A_in["wo"],
        "B_x": _B_in["x"],
        "B_w1": _B_in["w1"],
        "B_b1": _B_in["b1"],
        "B_w2": _B_in["w2"],
        "B_b2": _B_in["b2"],
    }

def reference(A_x, A_wqkv, A_w_phi, A_wo, B_x, B_w1, B_b1, B_w2, B_b2):
    def _A_ref(x, wqkv, w_phi, wo):
        B, S, D = x.shape
        H = 32; Dh = D // H
        qkv = (lambda x, *d: x.permute(*d))((x @ wqkv).reshape(B, S, 3, H, Dh), 2, 0, 3, 1, 4)
        q, k, v = qkv[0], qkv[1], qkv[2]
        pq = torch.einsum("bhsd,hdf->bhsf", q, w_phi)
        pk = torch.einsum("bhsd,hdf->bhsf", k, w_phi)
        phi_q = torch.concatenate([_softmax(pq, axis=-1), _softmax(-pq, axis=-1)], axis=-1)
        phi_k = torch.concatenate([_softmax(pk, axis=-1), _softmax(-pk, axis=-1)], axis=-1)
        kv = torch.einsum("bhsf,bhsd->bhfd", phi_k, v)
        z  = torch.einsum("bhsf->bhf", phi_k)
        num = torch.einsum("bhqf,bhfd->bhqd", phi_q, kv)
        den = torch.einsum("bhqf,bhf->bhq", phi_q, z)[..., None] + 1e-6
        o = num / den
        return (lambda x, *d: x.permute(*d))(o, 0, 2, 1, 3).reshape(B, S, D) @ wo

    def _B_ref(x, w1, b1, w2, b2):
        B, S, D = x.shape
        h = _layernorm(x, axis=-1)
        u = torch.einsum("bsd,sf->bdf", h, w1) + b1
        u = _gelu(u)
        y = torch.einsum("bdf,fs->bds", u, w2) + b2
        return (lambda x, *d: x.permute(*d))(y, 0, 2, 1)

    x = A_x
    x = x + _A_ref(_layernorm(x, axis=-1), A_wqkv, A_w_phi, A_wo)
    x = x + _B_ref(_layernorm(x, axis=-1), B_w1, B_b1, B_w2, B_b2)
    x = x + _A_ref(_layernorm(x, axis=-1), A_wqkv, A_w_phi, A_wo)
    x = x + _B_ref(_layernorm(x, axis=-1), B_w1, B_b1, B_w2, B_b2)
    return x
```

```cpp
#include <cuda_runtime.h>
#include <cuda.h>
#include <cuda_bf16.h>
#include <stdint.h>

namespace hk {
#define PFA 24
#define PFT 200

#define HOLDQ 0x060
#define HOLDO 0
#define XPF 1
#define MAPV 0
#define RB 1
#define BO(it) (RB == 0 || RB == 3 ? (it) : 0)
#define BH(it) (RB == 0 ? 2 + (it) : (RB == 1 ? 2 : (RB == 2 ? 1 - (it) : (it))))
#define BX (RB < 2 ? 4 : (RB == 2 ? 1 : 0))
#define BU(it) (RB == 0 ? (it) : 0)
#define DLX 0
#define DLO 0
#define DLH 0
#define DLU 0
#define DLL 400
#define DLK 0
#define DLW 0
#define P0S 0
#define WARM 1
#define WOD 1500
#define XDEL 0
#define RDL 700
#define HOLD4 0x40
template<int N, int TA, int TB> struct WG;
template<int N, int TA, int TB> struct WGZ;
template<int TA, int TB> struct WG<24,TA,TB> { template<uint32_t HA, uint32_t HB> static __device__ __forceinline__ void mma(float (&d)[12], uint32_t la, uint32_t lb){
  asm volatile("{\n.reg .pred p;\n.reg .b64 da, db;\nsetp.eq.b32 p, 0, 0;\nmov.b64 da, {%12, %14};\nmov.b64 db, {%13, %15};\nwgmma.mma_async.sync.aligned.m64n24k16.f32.bf16.bf16 {%0, %1, %2, %3, %4, %5, %6, %7, %8, %9, %10, %11}, da, db, p, 1, 1, %16, %17;\n}\n" : "+f"(d[0]), "+f"(d[1]), "+f"(d[2]), "+f"(d[3]), "+f"(d[4]), "+f"(d[5]), "+f"(d[6]), "+f"(d[7]), "+f"(d[8]), "+f"(d[9]), "+f"(d[10]), "+f"(d[11]) : "r"(la), "r"(lb), "n"(HA), "n"(HB), "n"(TA), "n"(TB));
} };
template<int TA, int TB> struct WG<128,TA,TB> { template<uint32_t HA, uint32_t HB> static __device__ __forceinline__ void mma(float (&d)[64], uint32_t la, uint32_t lb){
  asm volatile("{\n.reg .pred p;\n.reg .b64 da, db;\nsetp.eq.b32 p, 0, 0;\nmov.b64 da, {%64, %66};\nmov.b64 db, {%65, %67};\nwgmma.mma_async.sync.aligned.m64n128k16.f32.bf16.bf16 {%0, %1, %2, %3, %4, %5, %6, %7, %8, %9, %10, %11, %12, %13, %14, %15, %16, %17, %18, %19, %20, %21, %22, %23, %24, %25, %26, %27, %28, %29, %30, %31, %32, %33, %34, %35, %36, %37, %38, %39, %40, %41, %42, %43, %44, %45, %46, %47, %48, %49, %50, %51, %52, %53, %54, %55, %56, %57, %58, %59, %60, %61, %62, %63}, da, db, p, 1, 1, %68, %69;\n}\n" : "+f"(d[0]), "+f"(d[1]), "+f"(d[2]), "+f"(d[3]), "+f"(d[4]), "+f"(d[5]), "+f"(d[6]), "+f"(d[7]), "+f"(d[8]), "+f"(d[9]), "+f"(d[10]), "+f"(d[11]), "+f"(d[12]), "+f"(d[13]), "+f"(d[14]), "+f"(d[15]), "+f"(d[16]), "+f"(d[17]), "+f"(d[18]), "+f"(d[19]), "+f"(d[20]), "+f"(d[21]), "+f"(d[22]), "+f"(d[23]), "+f"(d[24]), "+f"(d[25]), "+f"(d[26]), "+f"(d[27]), "+f"(d[28]), "+f"(d[29]), "+f"(d[30]), "+f"(d[31]), "+f"(d[32]), "+f"(d[33]), "+f"(d[34]), "+f"(d[35]), "+f"(d[36]), "+f"(d[37]), "+f"(d[38]), "+f"(d[39]), "+f"(d[40]), "+f"(d[41]), "+f"(d[42]), "+f"(d[43]), "+f"(d[44]), "+f"(d[45]), "+f"(d[46]), "+f"(d[47]), "+f"(d[48]), "+f"(d[49]), "+f"(d[50]), "+f"(d[51]), "+f"(d[52]), "+f"(d[53]), "+f"(d[54]), "+f"(d[55]), "+f"(d[56]), "+f"(d[57]), "+f"(d[58]), "+f"(d[59]), "+f"(d[60]), "+f"(d[61]), "+f"(d[62]), "+f"(d[63]) : "r"(la), "r"(lb), "n"(HA), "n"(HB), "n"(TA), "n"(TB));
} };
template<int TA, int TB> struct WG<160,TA,TB> { template<uint32_t HA, uint32_t HB> static __device__ __forceinline__ void mma(float (&d)[80], uint32_t la, uint32_t lb){
  asm volatile("{\n.reg .pred p;\n.reg .b64 da, db;\nsetp.eq.b32 p, 0, 0;\nmov.b64 da, {%80, %82};\nmov.b64 db, {%81, %83};\nwgmma.mma_async.sync.aligned.m64n160k16.f32.bf16.bf16 {%0, %1, %2, %3, %4, %5, %6, %7, %8, %9, %10, %11, %12, %13, %14, %15, %16, %17, %18, %19, %20, %21, %22, %23, %24, %25, %26, %27, %28, %29, %30, %31, %32, %33, %34, %35, %36, %37, %38, %39, %40, %41, %42, %43, %44, %45, %46, %47, %48, %49, %50, %51, %52, %53, %54, %55, %56, %57, %58, %59, %60, %61, %62, %63, %64, %65, %66, %67, %68, %69, %70, %71, %72, %73, %74, %75, %76, %77, %78, %79}, da, db, p, 1, 1, %84, %85;\n}\n" : "+f"(d[0]), "+f"(d[1]), "+f"(d[2]), "+f"(d[3]), "+f"(d[4]), "+f"(d[5]), "+f"(d[6]), "+f"(d[7]), "+f"(d[8]), "+f"(d[9]), "+f"(d[10]), "+f"(d[11]), "+f"(d[12]), "+f"(d[13]), "+f"(d[14]), "+f"(d[15]), "+f"(d[16]), "+f"(d[17]), "+f"(d[18]), "+f"(d[19]), "+f"(d[20]), "+f"(d[21]), "+f"(d[22]), "+f"(d[23]), "+f"(d[24]), "+f"(d[25]), "+f"(d[26]), "+f"(d[27]), "+f"(d[28]), "+f"(d[29]), "+f"(d[30]), "+f"(d[31]), "+f"(d[32]), "+f"(d[33]), "+f"(d[34]), "+f"(d[35]), "+f"(d[36]), "+f"(d[37]), "+f"(d[38]), "+f"(d[39]), "+f"(d[40]), "+f"(d[41]), "+f"(d[42]), "+f"(d[43]), "+f"(d[44]), "+f"(d[45]), "+f"(d[46]), "+f"(d[47]), "+f"(d[48]), "+f"(d[49]), "+f"(d[50]), "+f"(d[51]), "+f"(d[52]), "+f"(d[53]), "+f"(d[54]), "+f"(d[55]), "+f"(d[56]), "+f"(d[57]), "+f"(d[58]), "+f"(d[59]), "+f"(d[60]), "+f"(d[61]), "+f"(d[62]), "+f"(d[63]), "+f"(d[64]), "+f"(d[65]), "+f"(d[66]), "+f"(d[67]), "+f"(d[68]), "+f"(d[69]), "+f"(d[70]), "+f"(d[71]), "+f"(d[72]), "+f"(d[73]), "+f"(d[74]), "+f"(d[75]), "+f"(d[76]), "+f"(d[77]), "+f"(d[78]), "+f"(d[79]) : "r"(la), "r"(lb), "n"(HA), "n"(HB), "n"(TA), "n"(TB));
} };
template<int TA, int TB> struct WGZ<24,TA,TB> { template<uint32_t HA, uint32_t HB> static __device__ __forceinline__ void mma(float (&d)[12], uint32_t la, uint32_t lb){
  asm volatile("{\n.reg .pred p;\n.reg .b64 da, db;\nsetp.ne.b32 p, 0, 0;\nmov.b64 da, {%12, %14};\nmov.b64 db, {%13, %15};\nwgmma.mma_async.sync.aligned.m64n24k16.f32.bf16.bf16 {%0, %1, %2, %3, %4, %5, %6, %7, %8, %9, %10, %11}, da, db, p, 1, 1, %16, %17;\n}\n" : "=f"(d[0]), "=f"(d[1]), "=f"(d[2]), "=f"(d[3]), "=f"(d[4]), "=f"(d[5]), "=f"(d[6]), "=f"(d[7]), "=f"(d[8]), "=f"(d[9]), "=f"(d[10]), "=f"(d[11]) : "r"(la), "r"(lb), "n"(HA), "n"(HB), "n"(TA), "n"(TB));
} };

constexpr int S_ = 2048, D_ = 640, F_ = 1536, SP = S_ + 64, DP = D_ + 64;
constexpr int NA = 10, A_SLOT = 8192, NB = 7, B_SLOT = 20480;
constexpr int OFF_A = 0, OFF_B = NA * A_SLOT, OFF_TAIL = OFF_B + NB * B_SLOT, OFF_MISC = OFF_TAIL + 4096;
constexpr int OFF_BAR = OFF_MISC;
constexpr int OFF_WB = OFF_BAR + 416, OFF_GA = OFF_BAR + 424;
constexpr int OFF_CS = OFF_MISC + 432;
constexpr int OFF_ST = OFF_CS + 1920;
constexpr int SMEM_BYTES = OFF_ST + 512;
static_assert(SMEM_BYTES <= 232448, "smem");

__device__ __align__(1024) uint8_t g_wp[160 * B_SLOT];
__device__ __align__(128) float g_cs[4 * 20 * 480];
__device__ __align__(128) float g_kv[8 * 7680];
__device__ __align__(1024) __nv_bfloat16 g_act[5 * SP * D_];
__device__ __align__(1024) __nv_bfloat16 g_u[2 * DP * F_];
__device__ __align__(128) uint4 g_ll[2 * 33 * 4 * 64];
__device__ __align__(128) float2 g_st[S_ * 4];
__device__ __align__(128) unsigned g_cnt[160 * 32];
__device__ __align__(128) unsigned g_epoch[1];
__device__ __align__(16) const uint32_t g_ident[400] = {0x3F80,0,0,0,0,0,0,0,0,0,0x3F800000,0,0,0,0,0,0,0,0,0,0,0x3F80,0,0,0,0,0,0,0,0,0,0x3F800000,0,0,0,0,0,0,0,0,0,0,0x3F80,0,0,0,0,0,0,0,0,0,0x3F800000,0,0,0,0,0,0,0,0,0,0,0x3F80,0,0,0,0,0,0,0,0,0,0x3F800000,0,0,0,0,0,0,0,0,0,0,0x3F80,0,0,0,0,0,0,0,0,0,0x3F800000,0,0,0,0,0,0,0,0,0,0,0x3F80,0,0,0,0,0,0,0,0,0,0x3F800000,0,0,0,0,0,0,0,0,0,0,0x3F80,0,0,0,0,0,0,0,0,0,0x3F800000,0,0,0,0,0,0,0,0,0,0,0x3F80,0,0,0,0,0,0,0,0,0,0x3F800000,0,0,0,0,0,0,0,0,0,0,0x3F80,0,0,0,0,0,0,0,0,0,0x3F800000,0,0,0,0,0,0,0,0,0,0,0x3F80,0,0,0,0,0,0,0,0,0,0x3F800000,0x3F80,0,0,0,0,0,0,0,0,0,0x3F800000,0,0,0,0,0,0,0,0,0,0,0x3F80,0,0,0,0,0,0,0,0,0,0x3F800000,0,0,0,0,0,0,0,0,0,0,0x3F80,0,0,0,0,0,0,0,0,0,0x3F800000,0,0,0,0,0,0,0,0,0,0,0x3F80,0,0,0,0,0,0,0,0,0,0x3F800000,0,0,0,0,0,0,0,0,0,0,0x3F80,0,0,0,0,0,0,0,0,0,0x3F800000,0,0,0,0,0,0,0,0,0,0,0x3F80,0,0,0,0,0,0,0,0,0,0x3F800000,0,0,0,0,0,0,0,0,0,0,0x3F80,0,0,0,0,0,0,0,0,0,0x3F800000,0,0,0,0,0,0,0,0,0,0,0x3F80,0,0,0,0,0,0,0,0,0,0x3F800000,0,0,0,0,0,0,0,0,0,0,0x3F80,0,0,0,0,0,0,0,0,0,0x3F800000,0,0,0,0,0,0,0,0,0,0,0x3F80,0,0,0,0,0,0,0,0,0,0x3F800000};
__device__ __forceinline__ int sm_rank(int s) {
  const int q = s - 64, rd = (q * 4682) >> 16;
  const int k = (s >> 1) & 7;
  return s < 64 ? (k ? 16 * k : 8) + 2 * (s >> 4) + (s & 1) : (s < 120 ? 16 * (1 + ((q - 14 * rd) >> 1)) + 8 + 2 * rd + (s & 1) : (MAPV == 3 ? (s < 128 ? s & 7 : -1) : (MAPV == 4 ? (s < 124 ? s & 3 : (s >= 128 ? (s & 3) + 4 : -1)) : (s >= 124 ? s & 7 : -1))));
}
#define PT(i)
#define PTL(i)
constexpr int C_W = 0, C_WO = 4, C_KV = 8, C_O = 16, C_H = 80, C_U = 88, C_X = 108;

__device__ __forceinline__ uint32_t s2u(const void* p) { return (uint32_t)__cvta_generic_to_shared(p); }
__device__ __forceinline__ void mbar_init(uint32_t a, int c) { asm volatile("mbarrier.init.shared::cta.b64 [%0], %1;" ::"r"(a), "r"(c)); }
__device__ __forceinline__ void mbar_expect(uint32_t a, uint32_t b) { asm volatile("mbarrier.arrive.expect_tx.shared::cta.b64 _, [%0], %1;" ::"r"(a), "r"(b) : "memory"); }
__device__ __forceinline__ void mbar_arrive(uint32_t a) { asm volatile("mbarrier.arrive.shared::cta.b64 _, [%0];" ::"r"(a) : "memory"); }
__device__ __forceinline__ void die() { asm volatile("trap;"); }
__device__ __forceinline__ void mbar_wait(uint32_t a, uint32_t ph) {
  asm volatile("{\n.reg .pred p, q;\n.reg .u32 n;\nmov.u32 n, 0;\n"
               "W%=: mbarrier.try_wait.parity.shared::cta.b64 p, [%0], %1;\n"
               "add.u32 n, n, 1;\nsetp.lt.and.u32 q, n, 2000000, !p;\n@q bra W%=;\n@!p trap;\n}" ::"r"(a), "r"(ph) : "memory");
}
__device__ __forceinline__ void wait_cnt3(int i0, int i1, int i2, unsigned target) {
  asm volatile("{\n.reg .pred p, q;\n.reg .u32 n, a, b, c;\nmov.u32 n, 0;\n"
               "W%=: ld.relaxed.gpu.global.u32 a, [%0];\nld.relaxed.gpu.global.u32 b, [%1];\nld.relaxed.gpu.global.u32 c, [%2];\n"
               "sub.u32 a, a, %3;\nsub.u32 b, b, %3;\nsub.u32 c, c, %3;\nor.b32 a, a, b;\nor.b32 a, a, c;\nsetp.ge.s32 p, a, 0;\n"
               "add.u32 n, n, 1;\nsetp.lt.and.u32 q, n, 4194304, !p;\n@q bra W%=;\n@!p trap;\n}"
               ::"l"(g_cnt + i0 * 32), "l"(g_cnt + i1 * 32), "l"(g_cnt + i2 * 32), "r"(target) : "memory");
}
__device__ __forceinline__ void wait_cnt(int idx, unsigned target) {
  const unsigned* p = g_cnt + idx * 32;
  asm volatile("{\n.reg .pred p, q;\n.reg .u32 n, v;\nmov.u32 n, 0;\n"
               "W%=: ld.relaxed.gpu.global.u32 v, [%0];\nsub.u32 v, v, %1;\nsetp.ge.s32 p, v, 0;\n"
               "add.u32 n, n, 1;\nsetp.lt.and.u32 q, n, 4194304, !p;\n@q bra W%=;\n@!p trap;\n}" ::"l"(p), "r"(target) : "memory");
}
__device__ __forceinline__ void ll_wait(const uint4* src, unsigned tag, float& fa, float& fb) {
  uint32_t a, b;
  asm volatile("{\n.reg .pred p, q;\n.reg .u32 n;\n.reg .b32 t0, t1;\nmov.u32 n, 0;\n"
               "W%=: ld.relaxed.gpu.global.v4.b32 {%0, t0, %1, t1}, [%2];\nsetp.eq.u32 p, t0, %3;\nsetp.eq.and.u32 p, t1, %3, p;\n@p bra D%=;\n"
               "add.u32 n, n, 1;\nsetp.gt.u32 q, n, 4194304;\n@q trap;\nbra W%=;\nD%=:\n}" : "=r"(a), "=r"(b) : "l"(src), "r"(tag) : "memory");
  fa = __uint_as_float(a); fb = __uint_as_float(b);
}
__device__ __forceinline__ void ll_wait2(const uint4* s0, const uint4* s1, unsigned tag, float (&fa)[2], float (&fb)[2]) {
  uint32_t a, b, c, d;
  asm volatile("{\n.reg .pred p, q;\n.reg .u32 n;\n.reg .b32 t0, t1, t2, t3;\nmov.u32 n, 0;\n"
               "W%=: ld.relaxed.gpu.global.v4.b32 {%0, t0, %1, t1}, [%4];\nld.relaxed.gpu.global.v4.b32 {%2, t2, %3, t3}, [%5];\n"
               "setp.eq.u32 p, t0, %6;\nsetp.eq.and.u32 p, t1, %6, p;\nsetp.eq.and.u32 p, t2, %6, p;\nsetp.eq.and.u32 p, t3, %6, p;\n@p bra D%=;\n"
               "add.u32 n, n, 1;\nsetp.gt.u32 q, n, 4194304;\n@q trap;\nbra W%=;\nD%=:\n}"
               : "=r"(a), "=r"(b), "=r"(c), "=r"(d) : "l"(s0), "l"(s1), "r"(tag) : "memory");
  fa[0] = __uint_as_float(a); fb[0] = __uint_as_float(b); fa[1] = __uint_as_float(c); fb[1] = __uint_as_float(d);
}
__device__ __forceinline__ void spin(int clk) {
  if (clk <= 0) return;
  const uint32_t t0 = (uint32_t)clock();
#pragma unroll 1
  while ((uint32_t)clock() - t0 < (uint32_t)clk) {}
}
__device__ __forceinline__ void red_rel(unsigned* p) { asm volatile("red.release.gpu.global.add.u32 [%0], 1;" ::"l"(p) : "memory"); }
__device__ __forceinline__ void fence_async() { asm volatile("fence.proxy.async.global;" ::: "memory"); }
__device__ __forceinline__ void fence_async_smem() { asm volatile("fence.proxy.async.shared::cta;" ::: "memory"); }
__device__ __forceinline__ void bar_sync(int id, int n) { asm volatile("bar.sync %0, %1;" ::"r"(id), "r"(n) : "memory"); }
__device__ __forceinline__ void bar_arrive(int id, int n) { asm volatile("bar.arrive %0, %1;" ::"r"(id), "r"(n) : "memory"); }
__device__ __forceinline__ void tma2d(uint32_t dst, const CUtensorMap* m, uint32_t bar, int c0, int c1) {
  asm volatile("cp.async.bulk.tensor.2d.shared::cluster.global.mbarrier::complete_tx::bytes [%0], [%1, {%3, %4}], [%2];"
               ::"r"(dst), "l"((uint64_t)m), "r"(bar), "r"(c0), "r"(c1) : "memory");
}
__device__ __forceinline__ void tma3d(uint32_t dst, const CUtensorMap* m, uint32_t bar, int c1, int c2) {
  asm volatile("cp.async.bulk.tensor.3d.shared::cluster.global.mbarrier::complete_tx::bytes [%0], [%1, {%3, %4, %5}], [%2];"
               ::"r"(dst), "l"((uint64_t)m), "r"(bar), "r"(0), "r"(c1), "r"(c2) : "memory");
}
__device__ __forceinline__ bool elect_one() {
  uint32_t p; asm volatile("{\n.reg .pred p;\nelect.sync _|p, 0xffffffff;\nselp.u32 %0, 1, 0, p;\n}" : "=r"(p)); return p != 0;
}
__device__ __forceinline__ void tma5d(uint32_t dst, const CUtensorMap* m, uint32_t bar, int c0, int c4) {
  asm volatile("cp.async.bulk.tensor.5d.shared::cluster.global.mbarrier::complete_tx::bytes [%0], [%1, {%3, %4, %4, %4, %5}], [%2];"
               ::"r"(dst), "l"((uint64_t)m), "r"(bar), "r"(c0), "r"(0), "r"(c4) : "memory");
}
__device__ __forceinline__ void bulk1d(uint32_t dst, const void* src, uint32_t bytes, uint32_t bar) {
  asm volatile("cp.async.bulk.shared::cluster.global.mbarrier::complete_tx::bytes [%0], [%1], %2, [%3];"
               ::"r"(dst), "l"(src), "r"(bytes), "r"(bar) : "memory");
}
__device__ __forceinline__ void prefetch_l2(const void* p, uint32_t bytes) {
  asm volatile("cp.async.bulk.prefetch.L2.global [%0], %1;" ::"l"(p), "r"(bytes) : "memory");
}
__device__ __forceinline__ uint32_t dlo(uint32_t addr, uint32_t lbo) { return ((addr & 0x3FFFF) >> 4) | ((lbo >> 4) << 16); }
__host__ __device__ constexpr uint32_t dhi(uint32_t sbo, bool sw) { return (sbo >> 4) | (sw ? 0x40000000u : 0u); }
__device__ __forceinline__ bool mbar_test(uint32_t a, uint32_t ph) {
  uint32_t ok;
  asm volatile("{\n.reg .pred p;\nmbarrier.test_wait.parity.shared::cta.b64 p, [%1], %2;\nselp.u32 %0, 1, 0, p;\n}" : "=r"(ok) : "r"(a), "r"(ph) : "memory");
  return ok != 0;
}
__device__ __forceinline__ void wg_fence() { asm volatile("wgmma.fence.sync.aligned;" ::: "memory"); }
__device__ __forceinline__ void wg_commit() { asm volatile("wgmma.commit_group.sync.aligned;" ::: "memory"); }
template <int N> __device__ __forceinline__ void wg_wait() { asm volatile("wgmma.wait_group.sync.aligned %0;" ::"n"(N) : "memory"); }
__device__ __forceinline__ uint32_t pack2(float lo, float hi) {
  uint32_t r; asm("cvt.rn.bf16x2.f32 %0, %1, %2;" : "=r"(r) : "f"(hi), "f"(lo)); return r;
}
__device__ __forceinline__ float bf_lo(uint32_t v) { return __uint_as_float(v << 16); }
__device__ __forceinline__ float bf_hi(uint32_t v) { return __uint_as_float(v & 0xffff0000u); }
__device__ __forceinline__ float ex2(float x) { float r; asm("ex2.approx.ftz.f32 %0, %1;" : "=f"(r) : "f"(x)); return r; }
__device__ __forceinline__ float rcp(float x) { float r; asm("rcp.approx.ftz.f32 %0, %1;" : "=f"(r) : "f"(x)); return r; }
__device__ __forceinline__ float rsq(float x) { float r; asm("rsqrt.approx.ftz.f32 %0, %1;" : "=f"(r) : "f"(x)); return r; }
__device__ __forceinline__ float tanh_ap(float x) { float r; asm("tanh.approx.f32 %0, %1;" : "=f"(r) : "f"(x)); return r; }
__device__ __forceinline__ void mma16816(float (&c)[4], uint32_t a0, uint32_t a1, uint32_t a2, uint32_t a3, uint32_t b0, uint32_t b1) {
  asm volatile("mma.sync.aligned.m16n8k16.row.col.f32.bf16.bf16.f32 {%0,%1,%2,%3}, {%4,%5,%6,%7}, {%8,%9}, {%0,%1,%2,%3};"
               : "+f"(c[0]), "+f"(c[1]), "+f"(c[2]), "+f"(c[3]) : "r"(a0), "r"(a1), "r"(a2), "r"(a3), "r"(b0), "r"(b1));
}
__device__ __forceinline__ void stsm4(uint32_t addr, uint32_t a, uint32_t b, uint32_t c, uint32_t d) {
  asm volatile("stmatrix.sync.aligned.m8n8.x4.shared.b16 [%0], {%1,%2,%3,%4};" ::"r"(addr), "r"(a), "r"(b), "r"(c), "r"(d) : "memory");
}
__device__ __forceinline__ void sts32(uint32_t a, uint32_t v) { asm volatile("st.shared.b32 [%0], %1;" ::"r"(a), "r"(v) : "memory"); }
__device__ __forceinline__ void sts64(uint32_t a, uint32_t v0, uint32_t v1) { asm volatile("st.shared.v2.b32 [%0], {%1,%2};" ::"r"(a), "r"(v0), "r"(v1) : "memory"); }
__device__ __forceinline__ void sts128(uint32_t a, uint32_t v0, uint32_t v1, uint32_t v2, uint32_t v3) {
  asm volatile("st.shared.v4.b32 [%0], {%1,%2,%3,%4};" ::"r"(a), "r"(v0), "r"(v1), "r"(v2), "r"(v3) : "memory");
}
__device__ __forceinline__ void stg128(void* p, uint32_t a, uint32_t b, uint32_t c, uint32_t d) {
  asm volatile("st.global.v4.b32 [%0], {%1,%2,%3,%4};" ::"l"(p), "r"(a), "r"(b), "r"(c), "r"(d) : "memory");
}
__device__ __forceinline__ uint4 lds128(uint32_t a) {
  uint4 v; asm volatile("ld.shared.v4.b32 {%0,%1,%2,%3}, [%4];" : "=r"(v.x), "=r"(v.y), "=r"(v.z), "=r"(v.w) : "r"(a) : "memory"); return v;
}
__device__ __forceinline__ float2 lds64f(uint32_t a) {
  float2 v; asm volatile("ld.shared.v2.f32 {%0,%1}, [%2];" : "=f"(v.x), "=f"(v.y) : "r"(a) : "memory"); return v;
}
__device__ __forceinline__ int perm32(int a) { return (a & ~0x1E) | ((a & 0x18) >> 2) | ((a & 0x06) << 2); }

constexpr uint64_t SEQ_K = 0x2103564210ull;
constexpr uint64_t SEQ_V = 0x2103521035ull;
constexpr int YS = 0, L3A = 13, L3B = 14;
constexpr uint64_t SEQ_Q = SEQ_V;
constexpr uint64_t SEQ_O = 0x0354621035ull;
constexpr uint64_t CYC_3 = 0x87BAEDCF9ull;
constexpr uint32_t CYC_4 = 0x4210356u;
constexpr uint32_t seq_mask(uint64_t s, int n) { uint32_t m = 0; for (int i = 0; i < n; i++) m ^= 1u << ((s >> (4 * i)) & 15); return m; }
constexpr uint32_t cyc_mask(uint32_t s, int n) { uint32_t m = 0; for (int i = 0; i < n; i++) m ^= 1u << ((s >> (4 * (i % 7))) & 15); return m; }
constexpr uint32_t MASK_K = seq_mask(SEQ_K, 10), MASK_V = seq_mask(SEQ_V, 10), MASK_Q = seq_mask(SEQ_Q, 10), MASK_O = seq_mask(SEQ_O, 10);
constexpr uint32_t MASK_4 = cyc_mask(CYC_4, 24);

struct Params {
  const __nv_bfloat16 *x, *wqkv, *wphi, *wo, *w1, *b1, *w2, *b2;
  __nv_bfloat16* out;
  int smap;
};

struct Ring {
  uint32_t sb;
  uint32_t ia, pa;
  uint32_t pb;
  __device__ __forceinline__ uint32_t parB(uint32_t s) const { return (pb >> s) & 1; }
  __device__ __forceinline__ uint32_t fullA(uint32_t s) const { return sb + OFF_BAR + s * 8; }
  __device__ __forceinline__ uint32_t emptyA(uint32_t s) const { return sb + OFF_BAR + 80 + s * 8; }
  __device__ __forceinline__ uint32_t fullB(uint32_t s) const { return sb + OFF_BAR + 160 + s * 8; }
  __device__ __forceinline__ uint32_t emptyB(uint32_t s) const { return sb + OFF_BAR + 288 + s * 8; }
  __device__ __forceinline__ uint32_t slotA(uint32_t s) const { return sb + OFF_A + s * A_SLOT; }
  __device__ __forceinline__ uint32_t slotB(uint32_t s) const { return sb + OFF_B + s * B_SLOT; }
  __device__ __forceinline__ void advA() { if (++ia == NA) { ia = 0; pa ^= 1; } }
  __device__ __forceinline__ void skipA(int n) { ia += n % NA; pa ^= (n / NA) & 1; if (ia >= NA) { ia -= NA; pa ^= 1; } }
};

__device__ __forceinline__ void ldsm4(uint32_t (&r)[4], uint32_t a) {
  asm volatile("ldmatrix.sync.aligned.m8n8.x4.shared.b16 {%0,%1,%2,%3}, [%4];" : "=r"(r[0]), "=r"(r[1]), "=r"(r[2]), "=r"(r[3]) : "r"(a) : "memory");
}
__device__ __forceinline__ void ldsm4t(uint32_t (&r)[4], uint32_t a) {
  asm volatile("ldmatrix.sync.aligned.m8n8.x4.trans.shared.b16 {%0,%1,%2,%3}, [%4];" : "=r"(r[0]), "=r"(r[1]), "=r"(r[2]), "=r"(r[3]) : "r"(a) : "memory");
}
constexpr int STG_W = 5760;
__device__ __forceinline__ void pack_unit(const Params& p, int mode, bool kvi, int grp, int chunk, int colbase, uint8_t* img, float* cs_out, int w, int lane, uint32_t stg, const void* pf) {
  const int g = lane >> 2, c = lane & 3, pr = w >> 1, hf = w & 1;
  const uint32_t pb = stg + 2560;
  {
    const __nv_bfloat16* W = ((mode == 2) ? p.wo : p.wqkv) + colbase + 40 * pr;
    const int ld = (mode == 2) ? D_ : 3 * D_;
    const uint2* ph = mode == 0 ? reinterpret_cast<const uint2*>(p.wphi) + (grp * 4 + pr) * 200 : reinterpret_cast<const uint2*>(g_ident);
#pragma unroll 1
    for (int q = lane; q < (P0S ? 160 : 200); q += 32) {
      const int sl = q / 5, pc = q - sl * 5;
      int row = chunk * 64 + 32 * hf + 8 * ((sl & 7) >> 1) + 2 * (sl >> 3) + (sl & 1);
      if (mode == 2) {
        const int gg = row / 160, kp = row - gg * 160, i = kp & 7;
        const int head = kp < 128 ? 2 * (kp >> 5) + (i >> 2) : 4 * ((kp - 128) >> 4) + (i >> 1);
        const int d = kp < 128 ? 8 * ((i >> 1) & 1) + 2 * ((kp >> 3) & 3) : 16 + 2 * ((kp >> 3) & 1);
        row = gg * 160 + head * 20 + d + (i & 1);
      }
      if (q < 160) asm volatile("cp.async.cg.shared.global [%0], [%1], 16;" ::"r"(stg + q * 16), "l"(W + (size_t)row * ld + pc * 8) : "memory");
      if (!P0S) {
        const uint32_t d = pb + sl * 80 + pc * 8, o = sl >= 20 ? 40 : 0;
        asm volatile("cp.async.ca.shared.global [%0], [%1], 8;" ::"r"(d + o), "l"(ph + q) : "memory");
        sts64(d + 40 - o, 0u, 0u);
      }
    }
    if (P0S) {
#pragma unroll 1
      for (int q = lane; q < 200; q += 32) {
        const uint32_t d = pb + (q / 5) * 40 + q * 8, o = q >= 100 ? 40 : 0;
        asm volatile("cp.async.ca.shared.global [%0], [%1], 8;" ::"r"(d + o), "l"(ph + q) : "memory");
        sts64(d + 40 - o, 0u, 0u);
      }
    }
    PT(4);
  }
#pragma unroll 1
  for (int pass = WARM ? 0 : 1; pass < 2; pass++) {
  if (pass) {
    asm volatile("cp.async.wait_all;" ::: "memory");
    if (pf) prefetch_l2(pf, 20480);
    __syncwarp();
    PT(6);
  }
  uint32_t a0[4], a1[4], a2[4], a3[4], a4[4];
  {
    const uint32_t la = pb + (lane & 7) * 80, mi = lane >> 3;
    ldsm4t(a0, la + (mi >> 1) * 640 + (mi & 1) * 16);
    ldsm4t(a1, la + 2 * 640 + mi * 16);
    ldsm4t(a2, la + (mi & 1) * 640 + (mi >> 1) * 3 * 640 + 32);
    ldsm4t(a3, la + (3 + (mi & 1)) * 640 + (3 + (mi >> 1)) * 16);
    ldsm4t(a4, la + 2 * 640 + 64);
  }
  uint32_t b4[4];
  ldsm4(b4, stg + lane * 80 + 64);
  uint32_t o[5][4];
#pragma unroll
  for (int tt = 0; tt < 4; tt++) {
    uint32_t b[4];
    ldsm4(b, stg + (8 * tt + (lane & 7)) * 80 + (lane >> 3) * 16);
    float c0[4] = {0.f, 0.f, 0.f, 0.f}, c1[4] = {0.f, 0.f, 0.f, 0.f}, c2[4] = {0.f, 0.f, 0.f, 0.f};
    mma16816(c0, a0[0], a0[1], a0[2], a0[3], b[0], b[1]);
    mma16816(c0, a1[0], a1[1], 0u, 0u, b[2], 0u);
    mma16816(c1, a2[0], 0u, a2[1], 0u, b[0], b[1]);
    mma16816(c1, a1[2], a1[3], a2[2], a3[0], b[2], b[3]);
    mma16816(c1, a2[3], a3[1], 0u, 0u, b4[tt], 0u);
    mma16816(c2, a4[0], 0u, a3[2], 0u, b[2], b[3]);
    mma16816(c2, a3[3], 0u, 0u, 0u, b4[tt], 0u);
    o[0][tt] = pack2(c0[0], c0[1]); o[1][tt] = pack2(c0[2], c0[3]); o[2][tt] = pack2(c1[0], c1[1]); o[3][tt] = pack2(c1[2], c1[3]); o[4][tt] = pack2(c2[0], c2[1]);
  }
#pragma unroll
  for (int r = 0; r < 5; r++) {
    const int m0 = g + 8 * r, m = 40 * pr + m0;
    const int hb = m0 >= 20;
    const int row = mode == 2 ? perm32(m) : (kvi ? 8 * ((m0 >> 1) + 10 * (mode - hb)) + 4 * (pr & 1) + 2 * hb : 8 * (m0 >> 1) + 2 * pr) + (m0 & 1);
    asm volatile("{\n.reg .pred p;\nsetp.ne.u32 p, %5, 0;\n@p st.global.v4.b32 [%0], {%1,%2,%3,%4};\n}"
                 ::"l"(img + row * 128 + (((4 * hf + c) ^ (row & 7)) << 4)), "r"(o[r][0]), "r"(o[r][1]), "r"(o[r][2]), "r"(o[r][3]), "r"(pass) : "memory");
  }
  if (mode != 2) {
#pragma unroll
    for (int r = 0; r < 5; r++) {
      float cs[4] = {0.f, 0.f, 0.f, 0.f};
      mma16816(cs, o[r][0], o[r][1], o[r][2], o[r][3], 0x3F803F80u, 0x3F803F80u);
      asm volatile("{\n.reg .pred p;\nsetp.ne.u32 p, %2, 0;\n@p st.global.f32 [%0], %1;\n}"
                   ::"l"(cs_out + hf * 480 + 40 * pr + g + 8 * r), "f"(cs[0] + cs[2]), "r"(c == 0 ? pass : 0) : "memory");
    }
  }
  }
}

__device__ __forceinline__ void arrive_if(uint32_t a, uint32_t p) {
  asm volatile("{\n.reg .pred p;\nsetp.ne.u32 p, %1, 0;\n@p mbarrier.arrive.shared::cta.b64 _, [%0];\n}" ::"r"(a), "r"(p) : "memory");
}
#define DEEPM 0
template <int ID, int N, int TA, int TB, bool CYC, bool WAIT_A, bool REL_A, bool ZERO = true>
__device__ __forceinline__ void gemm(float (&acc)[N / 2], Ring& r, uint64_t seq, int nch, uint32_t hold, int sig, bool elect, int pt = 0) {
  constexpr bool DEEP = (DEEPM >> ID) & 1;
  uint32_t ia = r.ia, pa = r.pa;
  uint32_t a1 = 0, b1 = 0, a2 = 0, b2 = 0;
  uint32_t e1 = 0, e2 = 0;
  const uint32_t em = elect ? 3u : 0u;
  uint32_t s = (uint32_t)seq & 15;
  const uint32_t la0 = dlo(r.slotA(0), TA ? 8192 : 16), lb0 = dlo(r.slotB(0), TB ? 8192 : 16) - (ID == 4 ? 7 * 1024 : 0);
#pragma unroll
  for (int i = 0; i < N / 2; i++) {
    if (ZERO) acc[i] = 0.f;
    else asm volatile("" : "+f"(acc[i]));
  }
  if (WAIT_A && ID == 5) mbar_wait(r.fullA(ia), pa);
  mbar_wait(r.fullB(s), r.parB(s));
  if (WAIT_A && ID != 5) mbar_wait(r.fullA(ia), pa);
  PT(pt);
#pragma unroll 1
  for (int i = nch - 1; i >= 0; i--) {
    const uint32_t la = la0 + ia * (A_SLOT >> 4), lb = lb0 + s * (ID == 4 ? 1024 : B_SLOT >> 4);
    wg_fence();
    WG<N, TA, TB>::template mma<dhi(1024, true), dhi(1024, true)>(acc, la, lb);
    const uint32_t a0 = r.emptyA(ia), b0 = r.emptyB(s), e0 = em & ~((hold & 1) << 1);
    hold >>= 1;
    r.pb ^= 1u << s;
    seq >>= 4;
    if (CYC) seq |= (uint64_t)s << (ID == 4 ? 32 : 24);
    s = (uint32_t)seq & 15;
    if (++ia == NA) { ia = 0; pa ^= 1; }
    bool ok = mbar_test(r.fullB(s), (r.pb >> s) & 1);
    if (WAIT_A) ok = mbar_test(r.fullA(ia), pa) && ok;
#pragma unroll
    for (int k = 1; k < 4; k++) WG<N, TA, TB>::template mma<dhi(1024, true), dhi(1024, true)>(acc, la + (TA ? 128 : 2) * k, lb + (TB ? 128 : 2) * k);
    wg_commit();
    if (i == 0 && sig) bar_arrive(sig, 256);
    if (DEEP) {
      wg_wait<2>();
      arrive_if(b2, e2 & 2);
      if (REL_A) arrive_if(a2, e2 & 1);
    } else {
      wg_wait<1>();
      arrive_if(b1, e1 & 2);
      if (REL_A) arrive_if(a1, e1 & 1);
    }
    if (!ok && i != 0) {
      if (DEEP) {
        wg_wait<1>();
        arrive_if(b1, e1 & 2);
        if (REL_A) arrive_if(a1, e1 & 1);
        e1 = 0;
      }
      if (WAIT_A) mbar_wait(r.fullA(ia), pa);
      mbar_wait(r.fullB(s), r.parB(s));
    }
    a2 = a1; b2 = b1; e2 = e1;
    a1 = a0; b1 = b0; e1 = e0;
  }
  if (DEEP) {
    wg_wait<1>();
    arrive_if(b2, e2 & 2);
    if (REL_A) arrive_if(a2, e2 & 1);
  }
  wg_wait<0>();
  arrive_if(b1, e1 & 2);
  if (REL_A) arrive_if(a1, e1 & 1);
}

__device__ __forceinline__ void softmax_regs(float (&acc)[80], uint32_t dst, uint32_t cs_addr, uint32_t st_addr, int nh) {
  float sc[2], nm[2];
#pragma unroll
  for (int rr = 0; rr < 2; rr++) { const float2 st = lds64f(st_addr + rr * 64); sc[rr] = st.y * 1.4426950408889634f; nm[rr] = -st.x; }
#pragma unroll 1
  for (int hb = 0; hb < nh; hb++) {
    float v[2][20], en[2][20];
#pragma unroll
    for (int b = 0; b < 5; b++) {
      const uint4 cv = lds128(cs_addr + b * 16);
#pragma unroll
      for (int rr = 0; rr < 2; rr++) {
        v[rr][4 * b + 0] = fmaf(nm[rr], __uint_as_float(cv.x), acc[8 * b + 2 * rr]);
        v[rr][4 * b + 1] = fmaf(nm[rr], __uint_as_float(cv.y), acc[8 * b + 2 * rr + 1]);
        v[rr][4 * b + 2] = fmaf(nm[rr], __uint_as_float(cv.z), acc[8 * b + 4 + 2 * rr]);
        v[rr][4 * b + 3] = fmaf(nm[rr], __uint_as_float(cv.w), acc[8 * b + 4 + 2 * rr + 1]);
      }
    }
    float ip[2], in[2];
#pragma unroll
    for (int rr = 0; rr < 2; rr++) {
      float mx[4], mn[4];
#pragma unroll
      for (int j = 0; j < 4; j++) {
        mx[j] = fmaxf(fmaxf(fmaxf(v[rr][j], v[rr][4 + j]), fmaxf(v[rr][8 + j], v[rr][12 + j])), v[rr][16 + j]);
        mn[j] = fminf(fminf(fminf(v[rr][j], v[rr][4 + j]), fminf(v[rr][8 + j], v[rr][12 + j])), v[rr][16 + j]);
      }
      const float M = -sc[rr] * fmaxf(fmaxf(mx[0], mx[1]), fmaxf(mx[2], mx[3])), m = sc[rr] * fminf(fminf(mn[0], mn[1]), fminf(mn[2], mn[3]));
      float sp[2] = {0.f, 0.f}, sn[2] = {0.f, 0.f};
#pragma unroll
      for (int i = 0; i < 20; i++) {
        en[rr][i] = ex2(fmaf(-sc[rr], v[rr][i], m)); v[rr][i] = ex2(fmaf(sc[rr], v[rr][i], M));
        sp[i & 1] += v[rr][i]; sn[i & 1] += en[rr][i];
      }
      ip[rr] = rcp(sp[0] + sp[1]); in[rr] = rcp(sn[0] + sn[1]);
    }
#pragma unroll
    for (int rr = 0; rr < 2; rr++)
#pragma unroll
      for (int b = 0; b < 5; b++)
        sts128(dst + b * 1024 + rr * 128, pack2(v[rr][4 * b] * ip[rr], en[rr][4 * b] * in[rr]), pack2(v[rr][4 * b + 1] * ip[rr], en[rr][4 * b + 1] * in[rr]),
               pack2(v[rr][4 * b + 2] * ip[rr], en[rr][4 * b + 2] * in[rr]), pack2(v[rr][4 * b + 3] * ip[rr], en[rr][4 * b + 3] * in[rr]));
    dst += 5120; cs_addr += 80;
#pragma unroll
    for (int i = 0; i < 40; i++) acc[i] = acc[40 + i];
  }
}
__device__ __forceinline__ void o_half(uint32_t sb, int hq, __nv_bfloat16* op, int lane) {
  const int c = lane & 3;
  float o[4][12];
  wg_fence();
#pragma unroll
  for (int hh = 0; hh < 4; hh++) {
    const int h = hq * 4 + hh;
    const uint32_t da = dlo(sb + OFF_A, 1024) + 5 * 64 * h + 2 * (h >> 1), db = dlo(sb + OFF_B + 4 * B_SLOT, 384) + 144 * h;
    WGZ<24, 0, 1>::mma<dhi(128, false), dhi(128, false)>(o[hh], da, db);
    WG<24, 0, 1>::mma<dhi(128, false), dhi(128, false)>(o[hh], da + 128, db + 48);
    WG<24, 0, 1>::mma<dhi(128, false), dhi(128, false)>(o[hh], da + 256, db + 96);
  }
  wg_commit();
  wg_wait<0>();
#pragma unroll
  for (int rr = 0; rr < 2; rr++) {
    uint32_t w[4][3];
#pragma unroll
    for (int hh = 0; hh < 4; hh++) {
      const float den = __shfl_sync(0xffffffffu, o[hh][8 + 2 * rr], (lane & ~3) | 2);
      const float inv = rcp(den + 1e-6f);
#pragma unroll
      for (int i = 0; i < 3; i++) w[hh][i] = pack2(o[hh][4 * i + 2 * rr] * inv, o[hh][4 * i + 2 * rr + 1] * inv);
    }
    __nv_bfloat16* orow = op + rr * 8 * D_;
    stg128(orow + (2 * hq) * 32 + c * 8, w[0][0], w[0][1], w[1][0], w[1][1]);
    stg128(orow + (2 * hq + 1) * 32 + c * 8, w[2][0], w[2][1], w[3][0], w[3][1]);
    if (c < 2) stg128(orow + 128 + hq * 16 + c * 8, w[0][2], w[1][2], w[2][2], w[3][2]);
  }
}

__global__ void __launch_bounds__(384, 1)
mega(const __grid_constant__ CUtensorMap tmX, const __grid_constant__ CUtensorMap tmAct, const __grid_constant__ CUtensorMap tmW1,
     const __grid_constant__ CUtensorMap tmW2, const __grid_constant__ CUtensorMap tmU, const Params p) {
  extern __shared__ __align__(1024) uint8_t smem[];
  const uint32_t sb = s2u(smem);
  const int tid = threadIdx.x, warp = __shfl_sync(0xffffffffu, tid >> 5, 0), lane = tid & 31, wg = warp >> 2;
  int rank;
  {
    unsigned smid, nsm;
    asm volatile("mov.u32 %0, %%smid;" : "=r"(smid));
    asm volatile("mov.u32 %0, %%nsmid;" : "=r"(nsm));
    const int bid = blockIdx.x;
    if (p.smap && nsm == 132) {
      rank = sm_rank(smid);
      if (rank < 0) {
        if (tid == 0) {
          unsigned e, v;
          asm volatile("ld.relaxed.gpu.global.u32 %0, [%1];" : "=r"(e) : "l"(g_epoch) : "memory");
#pragma unroll 1
          for (int i = 0; i < 4000; i++) {
            __nanosleep(1000);
            asm volatile("ld.relaxed.gpu.global.u32 %0, [%1];" : "=r"(v) : "l"(g_cnt + C_WO * 32) : "memory");
            if ((int)(v - (e + 1) * 136) >= 0) break;
          }
        }
        return;
      }
    } else {
      if ((bid & ~1) == 112 || bid >= 130) return;
      rank = bid < 112 ? bid : bid - 2;
    }
  }
  if (tid == 0) PT(0);
  const int sg = rank >> 4, li = rank & 15;
  const int t = 4 * sg + (li >> 2), g = li & 3;
  const bool has3 = li < 15;
  const int dt3 = 5 * (sg & 1) + li % 5, ft3 = 3 * (sg >> 1) + li / 5;
  auto signal = [&](int idx) { red_rel(g_cnt + idx * 32); };
  auto get_e1 = [&]() -> unsigned {
    unsigned e; asm volatile("ld.relaxed.gpu.global.u32 %0, [%1];" : "=r"(e) : "l"(g_epoch) : "memory");
    return e + 1;
  };
  Ring r; r.sb = sb; r.ia = 0; r.pa = 0; r.pb = 0;

  if (warp == 8) {
    if (elect_one()) {
#pragma unroll
      for (int i = 0; i < 54; i++) mbar_init(sb + OFF_BAR + i * 8, i < 10 || (i >= 20 && i < 36) || i >= 52 ? 1 : 4);
      fence_async_smem();
    }
    __syncwarp();
    bar_arrive(15, 96);
    if (sb & 1023) die();
    if (lane < 10) mbar_expect(r.fullA(lane), A_SLOT);
    if (lane == 0) asm volatile("prefetch.tensormap [%0];" ::"l"((uint64_t)&tmX) : "memory");
    __syncwarp();
    PTL(30);
    if (XDEL) spin(XDEL); else { bar_sync(0, 352); bar_arrive(11, 64); }
    if (elect_one()) {
#pragma unroll 1
      for (int i = 0; i < 10; i++) tma2d(r.slotA(i), &tmX, r.fullA(i), i * 64, t * 64);
    }
    __syncwarp();
    PTL(28);
    if (XDEL) { bar_sync(0, 352); bar_arrive(11, 64); }
  }
  if ((warp & ~1) != 8) {
    {
      int w = warp, mode = 2, grp, ch, colbase, sig = C_WO, u; float* cso = nullptr;
      if (warp < 8 && t < 30) {
        const int ty = t / 10;
        ch = t - ty * 10; grp = g; u = g * 30 + (ty == 2 ? 20 : (warp >> 2) * 10) + ch; mode = ty & 1; sig = C_W + g;
        colbase = (ty == 0 ? D_ : (ty == 1 ? 2 * D_ : 0)) + g * 160;
        cso = g_cs + (g * 10 + ch) * 960 + ty * 160;
        if (tid < 128) {
          const int e = t * 128 + tid, itz = e >= 1920;
          reinterpret_cast<float4*>(g_kv)[g * 1920 + e + itz * 5760] = make_float4(0.f, 0.f, 0.f, 0.f);
        }
      } else {
        int v = 2 * g + t - 30;
        if (warp >= 8) { const int j = 2 * rank + (warp & 1); v = 8 + (j >> 3); w = j & 7; }
        grp = v / 10; ch = v - grp * 10; u = 120 + v; colbase = grp * 160;
      }
      PT(5);
      if (warp >= 10) spin(WOD);
      pack_unit(p, mode, t < 20, grp, ch, colbase, g_wp + (size_t)u * B_SLOT, cso, w, lane, sb + OFF_B + warp * STG_W, XPF == 1 && tid == 0 ? p.x + (size_t)(t * 4 + g) * 10240 : nullptr);
      PT(7);
      if (warp < 8) bar_sync(1, 256);
      else { bar_arrive(0, 352); bar_sync(15, 96); }
      __syncwarp();
      if (lane == 0 && (warp == 0 || warp == 10)) signal(sig);
      __syncwarp();
      if (warp == 0) PTL(47);
      if (warp == 10) PTL(1);
    }
    if (warp < 8) bar_sync(0, 352);
    if (warp == 0) PTL(2);
  }

  if (wg == 2) {
    asm volatile("setmaxnreg.dec.sync.aligned.u32 56;");
    const uint32_t me = (warp >> 1) & 1;
    if (!(warp & 1)) {
      if (me) {
        mbar_wait(r.fullB(3), 0);
        if (elect_one()) {
#pragma unroll 1
          for (int i = 0; i < PFA; i++) {
            prefetch_l2(reinterpret_cast<const uint8_t*>(i < 12 ? p.w1 : p.w2) + ((size_t)(i < 12 ? i : i - 12) * 128 + rank) * 4096, 4096);
            __nanosleep(PFT);
          }
        }
        __syncwarp();
      }
      const unsigned e1 = get_e1();
      if (elect_one()) {
        uint32_t ia = me, pa = 0, pg = 0;
        auto adv = [&]() { ia += 2; if (ia >= NA) { ia -= NA; pa ^= 1; } };
        auto burst = [&](int f0, int f1, unsigned target, int c0, int c1, int d0, int d1, int pt, int dly) {
#pragma unroll 1
          for (int i = 0; i < 5; i++) { mbar_wait(r.emptyA(ia), pa); mbar_expect(r.fullA(ia), A_SLOT); adv(); }
          if (me == 0) { spin(dly); wait_cnt3(f0, f1, f1, target); mbar_arrive(sb + OFF_GA); PTL(pt); }
          else { mbar_wait(sb + OFF_GA, pg); pg ^= 1; c0 += d0; c1 += d1; }
          fence_async();
#pragma unroll 1
          for (int i = 0; i < 5; i++) {
            tma2d(r.slotA(ia), &tmAct, r.fullA(ia), c0, c1);
            c0 += 2 * d0; c1 += 2 * d1;
            ia += 2; if (ia >= NA) ia -= NA;
          }
        };
#pragma unroll 1
        for (int it = 0; it < 2; it++) {
          if (it) burst(C_X + t, C_X + t, e1 * 4, 0, BX * SP + t * 64, 64, 0, 28 + 48, DLX);
          burst(C_O + it * 32 + t, C_O + it * 32 + t, e1 * 4, 0, BO(it) * SP + t * 64, 64, 0, 29 + it * 48, DLO);
          if (has3) {
            burst(C_H + it * 4 + (dt3 * 64) / 160, C_H + it * 4 + (dt3 * 64 + 63) / 160, e1 * 32, dt3 * 64, BH(it) * SP, 0, 64, 31 + it * 48, DLH);
#pragma unroll 1
            for (int i = 10 + me; i < 32; i += 2) {
              mbar_wait(r.emptyA(ia), pa);
              mbar_expect(r.fullA(ia), A_SLOT); tma2d(r.slotA(ia), &tmAct, r.fullA(ia), dt3 * 64, BH(it) * SP + i * 64);
              adv();
            }
          }
#pragma unroll 1
          for (int i = me; i < 24; i += 2) {
            mbar_wait(r.emptyA(ia), pa);
            mbar_expect(r.fullA(ia), A_SLOT); tma5d(r.slotA(ia), &tmW2, r.fullA(ia), t * 64, i * 2);
            adv();
          }
        }
      }
    } else {
      r.pb = 0xffff;
      const unsigned e1 = get_e1();
      if (me == 0) {
        if (lane == 0) { spin(DLW); wait_cnt(C_W + g, e1 * 30); }
        __syncwarp();
        PTL(32);
        bar_sync(11, 64);
      }
      if (elect_one()) {
        auto acq = [&](uint32_t s, uint32_t bytes) {
          mbar_wait(r.emptyB(s), r.parB(s));
          r.pb ^= 1u << s;
          mbar_expect(r.fullB(s), bytes);
        };
        if (me == 0) mbar_arrive(sb + OFF_WB); else mbar_wait(sb + OFF_WB, 0);
        fence_async();
#pragma unroll 1
        for (int it = 0; it < 2; it++) {
#pragma unroll 1
          for (int ty = 0; ty < 4; ty++) {
            uint64_t seq = ty == 0 ? SEQ_K : (ty == 1 ? SEQ_V : (ty == 2 ? SEQ_Q : SEQ_O));
            const uint8_t* src = g_wp + (size_t)(ty < 3 ? g * 30 + ty * 10 : 120 + g * 10) * B_SLOT;
            if (it == 0 && ty == 3) { wait_cnt(C_WO, e1 * 136); fence_async(); }
#pragma unroll 1
            for (int i = 0; i < 10; i++) {
              const uint32_t s = (uint32_t)(seq & 15); seq >>= 4;
              if ((s & 1) == me) {
                acq(s, B_SLOT);
                bulk1d(r.slotB(s), src, B_SLOT, r.fullB(s));
              } else r.pb ^= 1u << s;
              src += B_SLOT;
            }
          }
          if (has3) {
            uint64_t cyc = CYC_3;
#pragma unroll 1
            for (int i = 0; i < 32; i++) {
              const uint32_t s = (uint32_t)cyc & 15; cyc = (cyc >> 4) | ((uint64_t)s << 32);
              if ((s & 1) == me) {
                if (i < 9) {
                  const uint32_t o0 = ((s - 7) * 13) >> 4, o1 = min(((s - 7) * 13 + 12) >> 4, 6u);
                  mbar_wait(r.emptyB(o0), r.parB(o0)); mbar_wait(r.emptyB(o1), r.parB(o1));
                }
                acq(s, 16384); tma3d(sb + OFF_B + (s - 7) * 16384, &tmW1, r.fullB(s), i * 64, ft3 * 2);
              } else r.pb ^= 1u << s;
            }
            if ((L3A & 1) == me) mbar_wait(r.emptyB(L3A), r.parB(L3A));
            mbar_wait(r.emptyB(L3B), r.parB(L3B));
          }
          uint32_t cyc = CYC_4;
#pragma unroll 1
          for (int i = 0; i < 7; i++) { const uint32_t s = cyc & 15; cyc = (cyc >> 4) | (s << 24); if ((s & 1) == me) acq(s, B_SLOT); else r.pb ^= 1u << s; }
          if (me) {
            const int f = C_U + it * 10 + (g * 160) / 64;
            spin(has3 ? DLU : DLU * 7);
            wait_cnt3(f, f + 1, f + 2, e1 * 12);
            mbar_arrive(sb + OFF_WB);
            PTL(33 + it * 48);
          } else mbar_wait(sb + OFF_WB, it ^ 1);
          fence_async();
#pragma unroll 1
          for (int i = 0; i < 24; i++) {
            const uint32_t s = cyc & 15; cyc = (cyc >> 4) | (s << 24);
            if ((s & 1) == me) {
              if (i >= 7) acq(s, B_SLOT);
              tma2d(r.slotB(s), &tmU, r.fullB(s), i * 64, BU(it) * DP + g * 160);
            } else if (i >= 7) r.pb ^= 1u << s;
          }
        }
      }
    }
  } else {
    asm volatile("setmaxnreg.inc.sync.aligned.u32 224;");
    const int w4 = warp & 3, gq = lane >> 2, c = lane & 3;
    const bool elect = lane == 0;
    const int row0 = w4 * 16 + gq;
    PT(3);
    const int t1 = tid - 128, wb = 4 + 2 * wg;
    unsigned e1 = 0;
    if (wg == 0) e1 = get_e1();
#pragma unroll 1
    for (int it = 0; it < 2; it++) {
      float acc[80];
      float* kvg = g_kv + (it * 4 + g) * 7680;
      if (wg) {
          if (it == 0) {
            const int row = w4 * 16 + (lane & 15), half = lane >> 4;
            float s1 = 0.f, s2 = 0.f, s3 = 0.f;
#pragma unroll 1
            for (int i = 0; i < 10; i++) {
              mbar_wait(r.fullA(i), 0);
              const uint32_t base = r.slotA(i) + row * 128;
#pragma unroll
              for (int j = 0; j < 4; j++) {
                const uint4 v = lds128(base + (((half * 4 + j) ^ (row & 7)) << 4));
                const uint32_t vv[4] = {v.x, v.y, v.z, v.w};
#pragma unroll
                for (int e = 0; e < 4; e++) { const float a = bf_lo(vv[e]), b = bf_hi(vv[e]); s1 += a + b; s2 = fmaf(a, a, s2); s3 = fmaf(b, b, s3); }
              }
            }
            s2 += s3;
            s1 += __shfl_xor_sync(0xffffffffu, s1, 16); s2 += __shfl_xor_sync(0xffffffffu, s2, 16);
            const float m = s1 * (1.f / D_), var = fmaxf(s2 * (1.f / D_) - m * m, 0.f);
            if (half == 0) sts64(sb + OFF_ST + row * 8, __float_as_uint(m), __float_as_uint(rsq(var + 1e-5f)));
            mbar_wait(sb + OFF_WB, 0);
            e1 = get_e1();
            if (t1 < 120) {
              float4 a = make_float4(0.f, 0.f, 0.f, 0.f);
#pragma unroll
              for (int ch = 0; ch < 20; ch++) {
                const float4 v = __ldcg(reinterpret_cast<const float4*>(g_cs + (g * 20 + ch) * 480) + t1);
                a.x += v.x; a.y += v.y; a.z += v.z; a.w += v.w;
              }
              sts128(sb + OFF_CS + t1 * 16, __float_as_uint(a.x), __float_as_uint(a.y), __float_as_uint(a.z), __float_as_uint(a.w));
            }
          } else {
            mbar_wait(r.fullA(r.ia), r.pa);
            if (t1 < 64) {
              const float4 u = __ldcg(reinterpret_cast<const float4*>(g_st + (t * 64 + t1) * 4)), v = __ldcg(reinterpret_cast<const float4*>(g_st + (t * 64 + t1) * 4) + 1);
              const float m = ((u.x + u.z) + (v.x + v.z)) * (1.f / D_), var = fmaxf(((u.y + u.w) + (v.y + v.w)) * (1.f / D_) - m * m, 0.f);
              sts64(sb + OFF_ST + t1 * 8, __float_as_uint(m), __float_as_uint(rsq(var + 1e-5f)));
            }
          }
          bar_arrive(2, 256);
          bar_sync(6, 128);
          PT(19 + it * 48);
          r.pb ^= MASK_K;
      }
#pragma unroll 1
      for (int ph = 0; ph < 2 - wg; ph++) {
        if (ph | wg) bar_sync(ph ? 12 : 7, 256);
        gemm<0, 160, 0, 0, false, true, false>(acc, r, ph ? SEQ_Q : (wg ? SEQ_V : SEQ_K), 10, ph ? HOLDQ : (wg ? YS * 8 : 0x18), ph ? 0 : (wg ? 12 : 7), elect,
                                               (ph ? 39 : (wg ? 38 : 34)) + it * 48);
        PT((ph ? 22 : (wg ? 20 : 8)) + it * 48);
        if (wg) { bar_arrive(14, 256); if (!YS) bar_sync(13, 256); }
        else { r.pb ^= ph ? 0u : MASK_V; bar_sync(ph ? 14 : 2, 256); }
        softmax_regs(acc, ph ? sb + OFF_A + c * (10240 + 32) + row0 * 16 : r.slotB(4) + (row0 ^ (2 * c)) * 16 + (YS * wg + c) * 5120,
                     sb + OFF_CS + (ph ? 1280 + c * 160 : (4 * wg + c) * 80), sb + OFF_ST + row0 * 8, ph + 1);
        PT((ph ? 23 : (wg ? 21 : 9)) + it * 48);
        if (ph) {
          fence_async_smem();
          break;
        }
        {
          float nm[2], rstd[2];
#pragma unroll
          for (int rr = 0; rr < 2; rr++) { const float2 st = lds64f(sb + OFF_ST + (row0 + 8 * rr) * 8); nm[rr] = -st.x; rstd[rr] = st.y; }
          const uint32_t vb = r.slotB(6) + (YS * wg + c) * 3072 + (row0 ^ (2 * c)) * 16;
          uint32_t w[2][10];
#pragma unroll
          for (int b = 0; b < 5; b++) {
            const uint4 cv = lds128(sb + OFF_CS + 640 + (4 * wg + c) * 80 + b * 16);
#pragma unroll
            for (int rr = 0; rr < 2; rr++) {
              const float* a = acc + 8 * b + 2 * rr;
              w[rr][2 * b] = pack2(rstd[rr] * fmaf(nm[rr], __uint_as_float(cv.x), a[0]), rstd[rr] * fmaf(nm[rr], __uint_as_float(cv.y), a[1]));
              w[rr][2 * b + 1] = pack2(rstd[rr] * fmaf(nm[rr], __uint_as_float(cv.z), a[4]), rstd[rr] * fmaf(nm[rr], __uint_as_float(cv.w), a[5]));
            }
          }
#pragma unroll
          for (int rr = 0; rr < 2; rr++) {
            sts128(vb + rr * 128, w[rr][0], w[rr][1], w[rr][2], w[rr][3]);
            sts128(vb + 1024 + rr * 128, w[rr][4], w[rr][5], w[rr][6], w[rr][7]);
            sts128(vb + 2048 + rr * 128, w[rr][8], w[rr][9], 0x00003F80u, 0u);
          }
        }
        fence_async_smem();
        bar_sync(wb, 128);
        PT((wg ? 10 : 43) + it * 48);
        {
          float kv[4][12];
          wg_fence();
#pragma unroll
          for (int hh = 0; hh < 4; hh++) {
            const int h = YS * wg + ((hh + t) & 3);
            const uint32_t da = dlo(r.slotB(4), 128) + 5 * 64 * h, db = dlo(r.slotB(6), 128) + 3 * 64 * h;
            WGZ<24, 1, 1>::mma<dhi(1024, false), dhi(1024, false)>(kv[hh], da, db);
#pragma unroll
            for (int ks = 1; ks < 4; ks++) WG<24, 1, 1>::mma<dhi(1024, false), dhi(1024, false)>(kv[hh], da + ks * 16, db + ks * 16);
          }
          wg_commit();
          wg_wait<0>();
          if (!wg && !YS) bar_arrive(13, 256);
          if (w4 < 2) {
#pragma unroll
            for (int hh = 0; hh < 4; hh++)
#pragma unroll
              for (int i = 0; i < 3; i++)
                if (i < 2 || c < 3)
                  asm volatile("red.global.add.v4.f32 [%0], {%1,%2,%3,%4};" ::"l"(kvg + (4 * wg + ((hh + t) & 3)) * 960 + (w4 * 3 + i) * 128 + lane * 4),
                               "f"(kv[hh][4 * i]), "f"(kv[hh][4 * i + 1]), "f"(kv[hh][4 * i + 2]), "f"(kv[hh][4 * i + 3]) : "memory");
          } else if (w4 == 2) {
#pragma unroll
            for (int hh = 0; hh < 4; hh++)
#pragma unroll
              for (int i = 0; i < 3; i++)
                if (i < 2 || c < 3)
                  asm volatile("red.global.add.v2.f32 [%0], {%1,%2};" ::"l"(kvg + (4 * wg + ((hh + t) & 3)) * 960 + 768 + i * 64 + lane * 2),
                               "f"(kv[hh][4 * i]), "f"(kv[hh][4 * i + 1]) : "memory");
          }
        }
        if (!wg) { bar_arrive(3, 256); PT(46 + it * 48); }
      }
      r.skipA(10);
      if (wg) {
        bar_sync(3, 256);
        PT(11 + it * 48);
        if (t1 == 0) { signal(C_KV + it * 4 + g); spin(DLK); wait_cnt(C_KV + it * 4 + g, e1 * 32); }
        if (w4 == 3) {
#pragma unroll
          for (int i = 0; i < 6; i++) {
            const int e = i * 32 + lane, h = e / 24, o = e - h * 24;
            sts128(r.slotB(4) + h * 2304 + 5 * 384 + o * 16, 0u, 0u, 0u, 0u);
          }
        }
        bar_sync(6, 128);
        PT(12 + it * 48);
        {
          const uint32_t kb = r.slotB(4) + w4 * 4608 + gq * 16 + c * 4;
          const float* src = kvg + w4 * 1920;
          float4 v[2][6];
          float2 u[2][3];
#pragma unroll
          for (int h = 0; h < 2; h++) {
#pragma unroll
            for (int j = 0; j < 6; j++) v[h][j] = __ldcg(reinterpret_cast<const float4*>(src + h * 960 + j * 128 + lane * 4));
#pragma unroll
            for (int i = 0; i < 3; i++) u[h][i] = __ldcg(reinterpret_cast<const float2*>(src + h * 960 + 768 + i * 64 + lane * 2));
          }
#pragma unroll
          for (int h = 0; h < 2; h++) {
#pragma unroll
            for (int j = 0; j < 6; j++) {
              sts32(kb + h * 2304 + (j / 3) * 768 + (j % 3) * 128, pack2(v[h][j].x, v[h][j].y));
              sts32(kb + h * 2304 + (j / 3) * 768 + 384 + (j % 3) * 128, pack2(v[h][j].z, v[h][j].w));
            }
#pragma unroll
            for (int i = 0; i < 3; i++) sts32(kb + h * 2304 + 4 * 384 + i * 128, pack2(u[h][i].x, u[h][i].y));
          }
        }
        if (elect) { if (YS) mbar_arrive(r.emptyB(5)); mbar_arrive(r.emptyB(6)); }
        fence_async_smem();
        PT(13 + it * 48);
      }
      bar_sync(5, 256);
      if (!wg) if (HOLDQ && lane < 10 && ((HOLDQ >> lane) & 1)) mbar_arrive(r.emptyB((uint32_t)(SEQ_Q >> (4 * lane)) & 15));
      if (!wg) PT(24 + it * 48);
      o_half(sb, wg, g_act + (size_t)(BO(it) * SP + t * 64 + row0) * D_ + g * 160, lane);
      if (!wg) PT(42 + it * 48);
      if (wg == 0) bar_arrive(13, 256);
      else {
        bar_sync(13, 256);
        if (lane < NA) mbar_arrive(r.emptyA(lane));
        if (lane == NA) mbar_arrive(r.emptyB(4));
        __syncwarp();
        if (t1 == 64) signal(C_O + it * 32 + t);
        __syncwarp();
      }
      if (wg == 0) {
        PT(25 + it * 48);
        spin(RDL);
        {
          const __nv_bfloat16* xr = (it ? g_act + (size_t)BX * SP * D_ : p.x) + (size_t)(t * 64 + row0) * D_ + g * 160 + c * 8;
#pragma unroll
          for (int rr = 0; rr < 2; rr++)
#pragma unroll
            for (int q = 0; q < 5; q++) {
              uint32_t v[4];
              asm volatile("ld.global.v4.b32 {%0,%1,%2,%3}, [%4];" : "=r"(v[0]), "=r"(v[1]), "=r"(v[2]), "=r"(v[3]) : "l"(xr + rr * 8 * D_ + q * 32) : "memory");
#pragma unroll
              for (int j = 0; j < 4; j++) { acc[4 * (4 * q + j) + 2 * rr] = bf_lo(v[j]); acc[4 * (4 * q + j) + 2 * rr + 1] = bf_hi(v[j]); }
            }
        }
        gemm<3, 160, 0, 0, false, true, true, false>(acc, r, SEQ_O, 10, HOLDO, 8, elect, 35 + it * 48);
        r.skipA(10);
        PT(14 + it * 48);
        {
          float s1[2] = {0.f, 0.f}, s2[2] = {0.f, 0.f};
#pragma unroll
          for (int rr = 0; rr < 2; rr++)
#pragma unroll
            for (int q = 0; q < 20; q++) {
              const float a = acc[4 * q + 2 * rr], b = acc[4 * q + 2 * rr + 1];
              s1[rr] += a + b; s2[rr] = fmaf(a, a, s2[rr]); s2[rr] = fmaf(b, b, s2[rr]);
            }
#pragma unroll
          for (int rr = 0; rr < 2; rr++) {
            s1[rr] += __shfl_xor_sync(0xffffffffu, s1[rr], 1); s2[rr] += __shfl_xor_sync(0xffffffffu, s2[rr], 1);
            s1[rr] += __shfl_xor_sync(0xffffffffu, s1[rr], 2); s2[rr] += __shfl_xor_sync(0xffffffffu, s2[rr], 2);
          }
          const unsigned tag = e1 * 2 + it;
          uint4* ll = g_ll + (size_t)(it * 33 + t) * 256;
          if (c < 2) {
            const float a = c ? s1[1] : s1[0], b = c ? s2[1] : s2[0];
            asm volatile("st.relaxed.gpu.global.v4.u32 [%0], {%1,%2,%3,%2};" ::"l"(ll + g * 64 + row0 + c * 8), "r"(__float_as_uint(a)), "r"(tag), "r"(__float_as_uint(b)) : "memory");
          }
          float o1[2], o2[2];
          spin(DLL);
          if (c < 3) {
            const uint4* src = ll + ((g + 1 + c) & 3) * 64 + row0;
            ll_wait2(src, src + 8, tag, o1, o2);
          } else { o1[0] = s1[0]; o1[1] = s1[1]; o2[0] = s2[0]; o2[1] = s2[1]; }
          __syncwarp();
          PT(15 + it * 48);
          __nv_bfloat16* hp = g_act + (size_t)(BH(it) * SP + t * 64 + row0) * D_ + g * 160 + c * 8;
#pragma unroll
          for (int rr = 0; rr < 2; rr++) {
            float a = o1[rr], b = o2[rr];
            a += __shfl_xor_sync(0xffffffffu, a, 1); b += __shfl_xor_sync(0xffffffffu, b, 1);
            a += __shfl_xor_sync(0xffffffffu, a, 2); b += __shfl_xor_sync(0xffffffffu, b, 2);
            const float m = a * (1.f / D_);
            const float var = fmaxf(b * (1.f / D_) - m * m, 0.f);
            const float r1 = rsq(var + 1e-5f);
            const float r2 = rsq(var * r1 * r1 + 1e-5f);
            const float sc = r1 * r2, of = -m * sc;
#pragma unroll
            for (int q = 0; q < 5; q++) {
              uint4 o;
              o.x = pack2(acc[16 * q + 2 * rr] * sc + of, acc[16 * q + 2 * rr + 1] * sc + of);
              o.y = pack2(acc[16 * q + 4 + 2 * rr] * sc + of, acc[16 * q + 4 + 2 * rr + 1] * sc + of);
              o.z = pack2(acc[16 * q + 8 + 2 * rr] * sc + of, acc[16 * q + 8 + 2 * rr + 1] * sc + of);
              o.w = pack2(acc[16 * q + 12 + 2 * rr] * sc + of, acc[16 * q + 12 + 2 * rr + 1] * sc + of);
              stg128(hp + rr * 8 * D_ + q * 32, o.x, o.y, o.z, o.w);
            }
          }
          PT(44 + it * 48);
          bar_sync(4, 128);
          if (tid == 0) signal(C_H + it * 4 + g);
          __syncwarp();
          if (HOLDO && lane < 10 && ((HOLDO >> lane) & 1)) mbar_arrive(r.emptyB((uint32_t)(SEQ_O >> (4 * lane)) & 15));
        }
        PT(16 + it * 48);
        {
          const float b2a = __bfloat162float(p.b2[t * 64 + row0]), b2b = __bfloat162float(p.b2[t * 64 + row0 + 8]);
#pragma unroll
          for (int q = 0; q < 20; q++) {
            const uint32_t v0 = pack2(acc[4 * q], acc[4 * q + 1]), v1 = pack2(acc[4 * q + 2], acc[4 * q + 3]);
            acc[4 * q] = bf_lo(v0) + b2a; acc[4 * q + 1] = bf_hi(v0) + b2a; acc[4 * q + 2] = bf_lo(v1) + b2b; acc[4 * q + 3] = bf_hi(v1) + b2b;
          }
        }
        if (has3) { r.skipA(32); bar_sync(9, 256); }
        gemm<5, 160, 1, 0, true, true, true, false>(acc, r, CYC_4, 24, (uint32_t)HOLD4 << 17, it == 0 ? 10 : 0, elect, 37 + it * 48);
        r.skipA(24);
        PT(17 + it * 48);
        {
          __nv_bfloat16* xp = (it ? p.out : g_act + (size_t)BX * SP * D_) + (size_t)(t * 64 + row0) * D_ + g * 160 + c * 8;
          uint32_t w[2][20];
#pragma unroll
          for (int rr = 0; rr < 2; rr++)
#pragma unroll
            for (int q = 0; q < 5; q++) {
#pragma unroll
              for (int j = 0; j < 4; j++) w[rr][4 * q + j] = pack2(acc[16 * q + 4 * j + 2 * rr], acc[16 * q + 4 * j + 2 * rr + 1]);
              stg128(xp + rr * 8 * D_ + q * 32, w[rr][4 * q], w[rr][4 * q + 1], w[rr][4 * q + 2], w[rr][4 * q + 3]);
            }
          if (it == 0) {
            float s1[2][2] = {{0.f, 0.f}, {0.f, 0.f}}, s2[2][2] = {{0.f, 0.f}, {0.f, 0.f}};
#pragma unroll
            for (int q = 0; q < 20; q++)
#pragma unroll
              for (int rr = 0; rr < 2; rr++) {
                const float a = bf_lo(w[rr][q]), b = bf_hi(w[rr][q]);
                s1[rr][0] += a; s1[rr][1] += b; s2[rr][0] = fmaf(a, a, s2[rr][0]); s2[rr][1] = fmaf(b, b, s2[rr][1]);
              }
            const bool hi = c & 1;
            float a = s1[0][0] + s1[0][1], b = s2[0][0] + s2[0][1], a2 = s1[1][0] + s1[1][1], b2 = s2[1][0] + s2[1][1];
            float ka = hi ? a2 : a, kb = hi ? b2 : b;
            ka += __shfl_xor_sync(0xffffffffu, hi ? a : a2, 1); kb += __shfl_xor_sync(0xffffffffu, hi ? b : b2, 1);
            ka += __shfl_xor_sync(0xffffffffu, ka, 2); kb += __shfl_xor_sync(0xffffffffu, kb, 2);
            if (c < 2) g_st[(t * 64 + row0 + c * 8) * 4 + g] = make_float2(ka, kb);

            bar_sync(4, 128);
            if (tid == 0) signal(C_X + t);
            __syncwarp();
            if (HOLD4 && lane < 7 && ((HOLD4 >> lane) & 1)) mbar_arrive(r.emptyB((uint32_t)(SEQ_K >> (4 * lane)) & 15));
          }
        }
        PT(18 + it * 48);
      } else {
        r.pb ^= MASK_Q;
        r.skipA(10); r.pb ^= MASK_O;
        if (!has3) bar_sync(8, 256);
        else {
          float a3[64];
          {
            const uint32_t* b1p = reinterpret_cast<const uint32_t*>(p.b1 + ft3 * 128) + c;
#pragma unroll
            for (int q = 0; q < 16; q++) {
              const uint32_t bb = __ldg(b1p + q * 4);
              a3[4 * q] = a3[4 * q + 2] = bf_lo(bb); a3[4 * q + 1] = a3[4 * q + 3] = bf_hi(bb);
            }
          }
          bar_sync(8, 256);
          gemm<4, 128, 1, 1, true, true, true, false>(a3, r, CYC_3, 32, 0, 9, elect, 36 + it * 48);
          r.skipA(32);
          PT(26 + it * 48);
#pragma unroll
          for (int rr = 0; rr < 2; rr++) {
            __nv_bfloat16* up = g_u + (size_t)(BU(it) * DP + perm32(dt3 * 64 + row0 + 8 * rr)) * F_ + ft3 * 128 + c * 8;
#pragma unroll
            for (int q = 0; q < 4; q++) {
              uint32_t w[4];
#pragma unroll
              for (int j = 0; j < 4; j++) {
                const float x0 = a3[4 * (4 * q + j) + 2 * rr], x1 = a3[4 * (4 * q + j) + 2 * rr + 1];
                const float i0 = x0 * (0.7978845608028654f + 0.035677408136300125f * x0 * x0);
                const float i1 = x1 * (0.7978845608028654f + 0.035677408136300125f * x1 * x1);
                const float h0 = 0.5f * x0, h1 = 0.5f * x1;
                w[j] = pack2(fmaf(h0, tanh_ap(i0), h0), fmaf(h1, tanh_ap(i1), h1));
              }
              stg128(up + q * 32, w[0], w[1], w[2], w[3]);
            }
          }
          PT(45 + it * 48);
          bar_sync(6, 128);
          if (t1 == 0) signal(C_U + it * 10 + dt3);
          PT(27 + it * 48);
        }
        r.skipA(24); r.pb ^= MASK_4;
        if (it == 0) bar_sync(10, 256);
      }
    }
    if (wg == 0) {
      if (rank == 0 && tid == 0) *reinterpret_cast<volatile unsigned*>(g_epoch) = e1;
    }
  }
}

typedef CUresult (*EncFn)(CUtensorMap*, CUtensorMapDataType, cuuint32_t, void*, const cuuint64_t*, const cuuint64_t*, const cuuint32_t*,
                          const cuuint32_t*, CUtensorMapInterleave, CUtensorMapSwizzle, CUtensorMapL2promotion, CUtensorMapFloatOOBfill);

static void enc(EncFn fn, CUtensorMap* tm, const void* base, int rank, const cuuint64_t* gd, const cuuint64_t* gs, const cuuint32_t* box) {
  cuuint32_t es[5] = {1, 1, 1, 1, 1};
  fn(tm, CU_TENSOR_MAP_DATA_TYPE_BFLOAT16, rank, const_cast<void*>(base), gd, gs, box, es, CU_TENSOR_MAP_INTERLEAVE_NONE,
     CU_TENSOR_MAP_SWIZZLE_128B, CU_TENSOR_MAP_L2_PROMOTION_L2_128B, CU_TENSOR_MAP_FLOAT_OOB_FILL_NONE);
}

}

extern "C" void kernel_launch(void* const* d_in, const int* in_sizes, int n_in, void* d_out, int out_size) {
  using namespace hk;
  static bool init = false;
  static CUtensorMap tmX, tmAct, tmW1, tmW2, tmU;
  static const void* cached[3] = {nullptr, nullptr, nullptr};
  static EncFn fn = nullptr;
  static int smap = 0;
  if (!init) {
    void* f = nullptr; cudaDriverEntryPointQueryResult qr;
    cudaGetDriverEntryPoint("cuTensorMapEncodeTiled", &f, cudaEnableDefault, &qr);
    fn = (EncFn)f;
    cudaFuncSetAttribute(mega, cudaFuncAttributeMaxDynamicSharedMemorySize, SMEM_BYTES);
    {
      int dev = 0, nsm = 0, n4 = 0, n8 = 0;
      cudaGetDevice(&dev);
      cudaDeviceGetAttribute(&nsm, cudaDevAttrMultiProcessorCount, dev);
      cudaLaunchConfig_t cfg = {};
      cfg.gridDim = dim3(128); cfg.blockDim = dim3(384); cfg.dynamicSmemBytes = SMEM_BYTES;
      cudaLaunchAttribute at[1];
      at[0].id = cudaLaunchAttributeClusterDimension; at[0].val.clusterDim.y = 1; at[0].val.clusterDim.z = 1;
      cfg.attrs = at; cfg.numAttrs = 1;
      at[0].val.clusterDim.x = 4; cudaOccupancyMaxActiveClusters(&n4, mega, &cfg);
      at[0].val.clusterDim.x = 8; cudaOccupancyMaxActiveClusters(&n8, mega, &cfg);
      cudaGetLastError();
      smap = nsm == 132 && n4 == 30 && n8 == 15;
    }
    void *pa, *pu;
    cudaGetSymbolAddress(&pa, g_act); cudaGetSymbolAddress(&pu, g_u);
    { cuuint64_t gd[2] = {D_, 5 * SP}, gs[1] = {D_ * 2}; cuuint32_t box[2] = {64, 64}; enc(fn, &tmAct, pa, 2, gd, gs, box); }
    { cuuint64_t gd[2] = {F_, 2 * DP}, gs[1] = {F_ * 2}; cuuint32_t box[2] = {64, 160}; enc(fn, &tmU, pu, 2, gd, gs, box); }
    init = true;
  }
  if (cached[0] != d_in[0] || cached[1] != d_in[5] || cached[2] != d_in[7]) {
    { cuuint64_t gd[2] = {D_, S_}, gs[1] = {D_ * 2}; cuuint32_t box[2] = {64, 64}; enc(fn, &tmX, d_in[0], 2, gd, gs, box); }
    { cuuint64_t gd[3] = {64, S_, F_ / 64}, gs[2] = {F_ * 2, 128}; cuuint32_t box[3] = {64, 64, 2}; enc(fn, &tmW1, d_in[5], 3, gd, gs, box); }
    { cuuint64_t gd[5] = {S_, 2, 4, 4, 48}, gs[4] = {S_ * 2, S_ * 2 * 8, S_ * 2 * 2, S_ * 2 * 32}; cuuint32_t box[5] = {64, 2, 4, 4, 2};
      enc(fn, &tmW2, d_in[7], 5, gd, gs, box); }
    cached[0] = d_in[0]; cached[1] = d_in[5]; cached[2] = d_in[7];
  }
  Params p;
  p.x = (const __nv_bfloat16*)d_in[0]; p.wqkv = (const __nv_bfloat16*)d_in[1]; p.wphi = (const __nv_bfloat16*)d_in[2];
  p.wo = (const __nv_bfloat16*)d_in[3]; p.w1 = (const __nv_bfloat16*)d_in[5]; p.b1 = (const __nv_bfloat16*)d_in[6];
  p.w2 = (const __nv_bfloat16*)d_in[7]; p.b2 = (const __nv_bfloat16*)d_in[8]; p.out = (__nv_bfloat16*)d_out; p.smap = smap;
  mega<<<132, 384, SMEM_BYTES, cudaStreamPerThread>>>(tmX, tmAct, tmW1, tmW2, tmU, p);
}
```
